```python
import torch

def _softmax(x, axis=-1):
    return torch.softmax(x, dim=axis)
def _gelu(x):
    return torch.nn.functional.gelu(x, approximate="tanh")
def _silu(x):
    return torch.nn.functional.silu(x)
def _sigmoid(x):
    return torch.sigmoid(x)
def _layernorm(x, axis=-1, eps=1e-5):
    m = x.mean(dim=axis, keepdim=True)
    v = x.var(dim=axis, keepdim=True, unbiased=False)
    return (x - m) / torch.sqrt(v + eps)
def _scatter_add(tgt, idx, src, axis=0):
    return tgt.clone().index_add_(axis, idx, src)
def _segment_sum(src, seg, n):
    out = torch.zeros((n,) + src.shape[1:], dtype=src.dtype)
    return out.index_add_(0, seg, src)
def _pad(x, pw):
    flat = tuple(v for pair in reversed(pw) for v in pair)
    return torch.nn.functional.pad(x, flat)

kernel_name = 'standalone__cross_network_dcn__recsys'

def setup_inputs():

    _w = (lambda a: (lambda t: t.to(torch.bfloat16) if t.is_floating_point() else t)(torch.as_tensor(a)))
    B, F, D, L = 16384, 26, 32, 3
    Din = min(F * D, 1024)
    return {
        "x0": _w((lambda *s: torch.randn(*s, dtype=torch.bfloat16) * 0.05)(B, Din)),
        "ws": _w((lambda *s: torch.randn(*s, dtype=torch.bfloat16) * 0.4)(L, Din, Din) * (Din ** -0.5)),
        "bs": _w((lambda *s: torch.randn(*s, dtype=torch.bfloat16) * 3.2)(L, Din) * 0.01),
    }

def reference(x0, ws, bs):
    x = x0
    L = ws.shape[0]
    for l in range(L):
        proj = torch.einsum('bd,de->be', x, ws[l]) + bs[l]
        x = x0 * proj + x
    return x
```

```cpp
#include <cuda_runtime.h>
#include <cuda.h>
#include <cuda_bf16.h>
#include <stdint.h>

namespace {

constexpr int BATCH = 16384;
constexpr int DIM = 832;
constexpr int NLAYER = 3;
constexpr int HALF_N = 416;
constexpr int NRB = BATCH / 128;
constexpr int NROUND = 2;
constexpr int NA = 7;
constexpr int A_BIG = 16384;
constexpr int A_SMALL = 8192;
constexpr int NW = 7;
constexpr int W0_STAGE = 3 * 2048;
constexpr int W1_STAGE = 4 * 2048;

constexpr int SMEM_AB = 0;
constexpr int SMEM_AS = SMEM_AB + NA * A_BIG;
constexpr int SMEM_W0 = SMEM_AS + A_SMALL;
constexpr int SMEM_W1 = SMEM_W0 + NW * W0_STAGE;
constexpr int SMEM_BIAS = SMEM_W1 + NW * W1_STAGE;
constexpr int SMEM_BAR = SMEM_BIAS + NLAYER * HALF_N * 2;
constexpr int NBAR = 4 * NW + 2 * (NA + 1) + 7 + 2 + 7;
constexpr int SMEM_TOTAL = SMEM_BAR + NBAR * 8;

constexpr int NTHREADS = 384;
#define ONEBUF 0
#define STORE_PACE_NS 400
#define LAG_BLOCK 4

__device__ __nv_bfloat16 g_scr[(size_t)(BATCH / NROUND) * DIM];
constexpr int FLAG_STRIDE = 64;
__device__ unsigned int g_flag[2 * NRB * 2 * FLAG_STRIDE];

#define TRACE(kind, idx) do {} while (0)
#define GT(idx) do {} while (0)

__device__ __forceinline__ uint32_t smem_u32(const void* p) { return (uint32_t)__cvta_generic_to_shared(p); }
__device__ __forceinline__ void mbar_init(uint32_t bar, int cnt) {
    asm volatile("mbarrier.init.shared::cta.b64 [%0], %1;" ::"r"(bar), "r"(cnt));
}
__device__ __forceinline__ void mbar_expect_tx(uint32_t bar, uint32_t bytes) {
    asm volatile("mbarrier.arrive.expect_tx.shared::cta.b64 _, [%0], %1;" ::"r"(bar), "r"(bytes) : "memory");
}
__device__ __forceinline__ void mbar_expect_tx_cluster(uint32_t bar_cluster, uint32_t bytes) {
    asm volatile("mbarrier.arrive.expect_tx.shared::cluster.b64 _, [%0], %1;" ::"r"(bar_cluster), "r"(bytes) : "memory");
}
__device__ __forceinline__ void mbar_arrive(uint32_t bar) {
    asm volatile("mbarrier.arrive.shared::cta.b64 _, [%0];" ::"r"(bar) : "memory");
}
__device__ __forceinline__ void mbar_arrive_if(uint32_t bar, bool pred) {
    asm volatile("{\n.reg .pred p;\nsetp.ne.u32 p, %1, 0;\n@p mbarrier.arrive.shared::cta.b64 _, [%0];\n}\n" ::"r"(bar),
                 "r"((uint32_t)pred) : "memory");
}
__device__ __forceinline__ void mbar_arrive_cluster_if(uint32_t bar_cluster, bool pred) {
    asm volatile("{\n.reg .pred p;\nsetp.ne.u32 p, %1, 0;\n@p mbarrier.arrive.shared::cluster.b64 _, [%0];\n}\n" ::"r"(
                     bar_cluster), "r"((uint32_t)pred) : "memory");
}
__device__ __forceinline__ bool mbar_test(uint32_t bar, uint32_t parity) {
    uint32_t ok;
    asm volatile(
        "{\n.reg .pred p;\nmbarrier.test_wait.parity.shared::cta.b64 p, [%1], %2;\nselp.b32 %0, 1, 0, p;\n}\n"
        : "=r"(ok) : "r"(bar), "r"(parity) : "memory");
    return ok;
}
__device__ __forceinline__ void mbar_wait(uint32_t bar, uint32_t parity) {
    asm volatile(
        "{\n.reg .pred P1;\n.reg .u32 cnt;\n"
        "mbarrier.try_wait.parity.shared::cta.b64 P1, [%0], %1;\n"
        "@P1 bra DONE;\n"
        "mov.u32 cnt, 0;\n"
        "LAB_WAIT:\n"
        "mbarrier.try_wait.parity.shared::cta.b64 P1, [%0], %1;\n"
        "@P1 bra DONE;\n"
        "add.u32 cnt, cnt, 1;\n"
        "setp.lt.u32 P1, cnt, 4194304;\n"
        "@P1 bra LAB_WAIT;\n"
        "trap;\n"
        "DONE:\n}\n" ::"r"(bar), "r"(parity)
        : "memory");
}
__device__ __forceinline__ bool elect_one() {
    uint32_t p;
    asm volatile("{\n.reg .pred P;\nelect.sync _|P, 0xffffffff;\nselp.b32 %0, 1, 0, P;\n}\n" : "=r"(p));
    return p;
}
__device__ __forceinline__ void wait_flag(const unsigned int* flag, unsigned int target) {
    asm volatile(
        "{\n.reg .pred P1;\n.reg .u32 cnt, v;\n"
        "mov.u32 cnt, 0;\n"
        "LAB_WAIT:\n"
        "ld.acquire.gpu.global.u32 v, [%0];\n"
        "setp.ge.u32 P1, v, %1;\n"
        "@P1 bra DONE;\n"
        "nanosleep.u32 200;\n"
        "add.u32 cnt, cnt, 1;\n"
        "setp.lt.u32 P1, cnt, 4194304;\n"
        "@P1 bra LAB_WAIT;\n"
        "trap;\n"
        "DONE:\n}\n" ::"l"(flag), "r"(target)
        : "memory");
}
__device__ __forceinline__ int lane_id() {
    int l;
    asm volatile("mov.u32 %0, %%laneid;" : "=r"(l));
    return l;
}
__device__ __forceinline__ void lds64(uint32_t (&v)[2], uint32_t addr) {
    asm volatile("ld.shared.v2.u32 {%0,%1}, [%2];" : "=r"(v[0]), "=r"(v[1]) : "r"(addr));
}
__device__ __forceinline__ uint32_t mapa(uint32_t addr, uint32_t rank) {
    uint32_t r;
    asm volatile("mapa.shared::cluster.u32 %0, %1, %2;" : "=r"(r) : "r"(addr), "r"(rank));
    return r;
}
__device__ __forceinline__ void tma2d_ld(uint32_t dst, const CUtensorMap* tm, int c0, int c1, uint32_t bar) {
    asm volatile(
        "cp.async.bulk.tensor.2d.shared::cluster.global.mbarrier::complete_tx::bytes [%0], [%1, {%3, %4}], [%2];" ::"r"(dst),
        "l"(tm), "r"(bar), "r"(c0), "r"(c1)
        : "memory");
}
__device__ __forceinline__ void tma2d_st(const CUtensorMap* tm, int c0, int c1, uint32_t src) {
    asm volatile("cp.async.bulk.tensor.2d.global.shared::cta.bulk_group [%0, {%2, %3}], [%1];" ::"l"(tm), "r"(src),
                 "r"(c0), "r"(c1)
                 : "memory");
}
__device__ __forceinline__ void tma3d_mc(uint32_t dst, const CUtensorMap* tm, int c0, int c1, int c2, uint32_t bar,
                                         uint16_t mask) {
    asm volatile(
        "cp.async.bulk.tensor.3d.shared::cluster.global.mbarrier::complete_tx::bytes.multicast::cluster "
        "[%0], [%1, {%3, %4, %5}], [%2], %6;" ::"r"(dst), "l"(tm), "r"(bar), "r"(c0), "r"(c1), "r"(c2), "h"(mask)
        : "memory");
}
__device__ __forceinline__ void cluster_sync_all() {
    asm volatile("barrier.cluster.arrive.release.aligned;\nbarrier.cluster.wait.acquire.aligned;" ::: "memory");
}
__device__ __forceinline__ uint64_t mkdesc(uint32_t addr, uint32_t lbo, uint32_t sbo, uint32_t swz) {
    uint64_t d = 0;
    d |= (uint64_t)((addr & 0x3FFFF) >> 4);
    d |= (uint64_t)((lbo & 0x3FFFF) >> 4) << 16;
    d |= (uint64_t)((sbo & 0x3FFFF) >> 4) << 32;
    d |= (uint64_t)swz << 62;
    return d;
}

__device__ __forceinline__ void wgmma_n192(float (&d)[96], uint64_t da, uint64_t db) {
    asm volatile(
        "{\n.reg .pred p;\nsetp.eq.u32 p, 0, 0;\n"
        "wgmma.mma_async.sync.aligned.m64n192k16.f32.bf16.bf16 "
        "{%0, %1, %2, %3, %4, %5, %6, %7, %8, %9, %10, %11, %12, %13, %14, %15, "
        "%16, %17, %18, %19, %20, %21, %22, %23, %24, %25, %26, %27, %28, %29, %30, %31, "
        "%32, %33, %34, %35, %36, %37, %38, %39, %40, %41, %42, %43, %44, %45, %46, %47, "
        "%48, %49, %50, %51, %52, %53, %54, %55, %56, %57, %58, %59, %60, %61, %62, %63, "
        "%64, %65, %66, %67, %68, %69, %70, %71, %72, %73, %74, %75, %76, %77, %78, %79, "
        "%80, %81, %82, %83, %84, %85, %86, %87, %88, %89, %90, %91, %92, %93, %94, %95}, %96, %97, p, 1, 1, 0, 1;\n}\n"
        : "+f"(d[0]), "+f"(d[1]), "+f"(d[2]), "+f"(d[3]), "+f"(d[4]), "+f"(d[5]), "+f"(d[6]), "+f"(d[7]),
          "+f"(d[8]), "+f"(d[9]), "+f"(d[10]), "+f"(d[11]), "+f"(d[12]), "+f"(d[13]), "+f"(d[14]), "+f"(d[15]),
          "+f"(d[16]), "+f"(d[17]), "+f"(d[18]), "+f"(d[19]), "+f"(d[20]), "+f"(d[21]), "+f"(d[22]), "+f"(d[23]),
          "+f"(d[24]), "+f"(d[25]), "+f"(d[26]), "+f"(d[27]), "+f"(d[28]), "+f"(d[29]), "+f"(d[30]), "+f"(d[31]),
          "+f"(d[32]), "+f"(d[33]), "+f"(d[34]), "+f"(d[35]), "+f"(d[36]), "+f"(d[37]), "+f"(d[38]), "+f"(d[39]),
          "+f"(d[40]), "+f"(d[41]), "+f"(d[42]), "+f"(d[43]), "+f"(d[44]), "+f"(d[45]), "+f"(d[46]), "+f"(d[47]),
          "+f"(d[48]), "+f"(d[49]), "+f"(d[50]), "+f"(d[51]), "+f"(d[52]), "+f"(d[53]), "+f"(d[54]), "+f"(d[55]),
          "+f"(d[56]), "+f"(d[57]), "+f"(d[58]), "+f"(d[59]), "+f"(d[60]), "+f"(d[61]), "+f"(d[62]), "+f"(d[63]),
          "+f"(d[64]), "+f"(d[65]), "+f"(d[66]), "+f"(d[67]), "+f"(d[68]), "+f"(d[69]), "+f"(d[70]), "+f"(d[71]),
          "+f"(d[72]), "+f"(d[73]), "+f"(d[74]), "+f"(d[75]), "+f"(d[76]), "+f"(d[77]), "+f"(d[78]), "+f"(d[79]),
          "+f"(d[80]), "+f"(d[81]), "+f"(d[82]), "+f"(d[83]), "+f"(d[84]), "+f"(d[85]), "+f"(d[86]), "+f"(d[87]),
          "+f"(d[88]), "+f"(d[89]), "+f"(d[90]), "+f"(d[91]), "+f"(d[92]), "+f"(d[93]), "+f"(d[94]), "+f"(d[95])
        : "l"(da), "l"(db));
}
__device__ __forceinline__ void wgmma_n224(float (&d)[112], uint64_t da, uint64_t db) {
    asm volatile(
        "{\n.reg .pred p;\nsetp.eq.u32 p, 0, 0;\n"
        "wgmma.mma_async.sync.aligned.m64n224k16.f32.bf16.bf16 "
        "{%0, %1, %2, %3, %4, %5, %6, %7, %8, %9, %10, %11, %12, %13, %14, %15, "
        "%16, %17, %18, %19, %20, %21, %22, %23, %24, %25, %26, %27, %28, %29, %30, %31, "
        "%32, %33, %34, %35, %36, %37, %38, %39, %40, %41, %42, %43, %44, %45, %46, %47, "
        "%48, %49, %50, %51, %52, %53, %54, %55, %56, %57, %58, %59, %60, %61, %62, %63, "
        "%64, %65, %66, %67, %68, %69, %70, %71, %72, %73, %74, %75, %76, %77, %78, %79, "
        "%80, %81, %82, %83, %84, %85, %86, %87, %88, %89, %90, %91, %92, %93, %94, %95, "
        "%96, %97, %98, %99, %100, %101, %102, %103, %104, %105, %106, %107, %108, %109, %110, %111}, %112, %113, p, 1, 1, 0, 1;\n}\n"
        : "+f"(d[0]), "+f"(d[1]), "+f"(d[2]), "+f"(d[3]), "+f"(d[4]), "+f"(d[5]), "+f"(d[6]), "+f"(d[7]),
          "+f"(d[8]), "+f"(d[9]), "+f"(d[10]), "+f"(d[11]), "+f"(d[12]), "+f"(d[13]), "+f"(d[14]), "+f"(d[15]),
          "+f"(d[16]), "+f"(d[17]), "+f"(d[18]), "+f"(d[19]), "+f"(d[20]), "+f"(d[21]), "+f"(d[22]), "+f"(d[23]),
          "+f"(d[24]), "+f"(d[25]), "+f"(d[26]), "+f"(d[27]), "+f"(d[28]), "+f"(d[29]), "+f"(d[30]), "+f"(d[31]),
          "+f"(d[32]), "+f"(d[33]), "+f"(d[34]), "+f"(d[35]), "+f"(d[36]), "+f"(d[37]), "+f"(d[38]), "+f"(d[39]),
          "+f"(d[40]), "+f"(d[41]), "+f"(d[42]), "+f"(d[43]), "+f"(d[44]), "+f"(d[45]), "+f"(d[46]), "+f"(d[47]),
          "+f"(d[48]), "+f"(d[49]), "+f"(d[50]), "+f"(d[51]), "+f"(d[52]), "+f"(d[53]), "+f"(d[54]), "+f"(d[55]),
          "+f"(d[56]), "+f"(d[57]), "+f"(d[58]), "+f"(d[59]), "+f"(d[60]), "+f"(d[61]), "+f"(d[62]), "+f"(d[63]),
          "+f"(d[64]), "+f"(d[65]), "+f"(d[66]), "+f"(d[67]), "+f"(d[68]), "+f"(d[69]), "+f"(d[70]), "+f"(d[71]),
          "+f"(d[72]), "+f"(d[73]), "+f"(d[74]), "+f"(d[75]), "+f"(d[76]), "+f"(d[77]), "+f"(d[78]), "+f"(d[79]),
          "+f"(d[80]), "+f"(d[81]), "+f"(d[82]), "+f"(d[83]), "+f"(d[84]), "+f"(d[85]), "+f"(d[86]), "+f"(d[87]),
          "+f"(d[88]), "+f"(d[89]), "+f"(d[90]), "+f"(d[91]), "+f"(d[92]), "+f"(d[93]), "+f"(d[94]), "+f"(d[95]),
          "+f"(d[96]), "+f"(d[97]), "+f"(d[98]), "+f"(d[99]), "+f"(d[100]), "+f"(d[101]), "+f"(d[102]), "+f"(d[103]),
          "+f"(d[104]), "+f"(d[105]), "+f"(d[106]), "+f"(d[107]), "+f"(d[108]), "+f"(d[109]), "+f"(d[110]), "+f"(d[111])
        : "l"(da), "l"(db));
}
__device__ __forceinline__ void wgmma_fence() { asm volatile("wgmma.fence.sync.aligned;" ::: "memory"); }
__device__ __forceinline__ void wgmma_commit() { asm volatile("wgmma.commit_group.sync.aligned;" ::: "memory"); }
template <int N>
__device__ __forceinline__ void wgmma_wait() { asm volatile("wgmma.wait_group.sync.aligned %0;" ::"n"(N) : "memory"); }

__device__ __forceinline__ uint32_t pack_bf16(float lo, float hi) {
    uint32_t r;
    asm("cvt.rn.bf16x2.f32 %0, %1, %2;" : "=r"(r) : "f"(hi), "f"(lo));
    return r;
}
__device__ __forceinline__ uint32_t fma_bf16x2(uint32_t a, uint32_t b, uint32_t c) {
    uint32_t r;
    asm("fma.rn.bf16x2 %0, %1, %2, %3;" : "=r"(r) : "r"(a), "r"(b), "r"(c));
    return r;
}
__device__ __forceinline__ void ldsm_x4(uint32_t (&v)[4], uint32_t addr) {
    asm volatile("ldmatrix.sync.aligned.m8n8.x4.shared.b16 {%0,%1,%2,%3}, [%4];"
                 : "=r"(v[0]), "=r"(v[1]), "=r"(v[2]), "=r"(v[3]) : "r"(addr) : "memory");
}
__device__ __forceinline__ void stsm_x4(uint32_t addr, const uint32_t (&v)[4]) {
    asm volatile("stmatrix.sync.aligned.m8n8.x4.shared.b16 [%0], {%1,%2,%3,%4};" ::"r"(addr), "r"(v[0]), "r"(v[1]),
                 "r"(v[2]), "r"(v[3]) : "memory");
}

__device__ __forceinline__ void epi_pair(uint32_t& x, float a0, float a1, uint32_t bias) {
    asm volatile(
        "{\n.reg .b32 t;\n"
        "cvt.rn.bf16x2.f32 t, %2, %1;\n"
        "add.rn.bf16x2 t, t, %3;\n"
        "fma.rn.bf16x2 %0, %0, t, %0;\n}\n"
        : "+r"(x) : "f"(a0), "f"(a1), "r"(bias));
}
__device__ __forceinline__ void lds128(uint32_t (&v)[4], uint32_t addr) {
    asm volatile("ld.shared.v4.u32 {%0,%1,%2,%3}, [%4];" : "=r"(v[0]), "=r"(v[1]), "=r"(v[2]), "=r"(v[3]) : "r"(addr));
}

__device__ __forceinline__ int big_col(int half, int i) { return (half ? 448 : 0) + 64 * i; }
__device__ __forceinline__ int small_col(int half) { return half ? 416 : 384; }

struct Maps {
    CUtensorMap x0b, x0s, outb, outs, scrb, scrs, wb, wsm;
};

template <int N> struct MMA;
template <> struct MMA<192> {
    static __device__ __forceinline__ void run(float (&d)[96], uint64_t a, uint64_t b) { wgmma_n192(d, a, b); }
};
template <> struct MMA<224> {
    static __device__ __forceinline__ void run(float (&d)[112], uint64_t a, uint64_t b) { wgmma_n224(d, a, b); }
};

template <int WG>
__device__ __forceinline__ void consumer(const uint32_t sbase, const int w) {
    constexpr int N = WG == 0 ? 192 : 224;
    constexpr int WSTAGE = WG == 0 ? W0_STAGE : W1_STAGE;
    const uint32_t bar_wfull = sbase + SMEM_BAR + WG * NW * 8;
    const uint32_t afull = sbase + SMEM_BAR + 4 * NW * 8;
    const uint32_t aempty = afull + (NA + 1) * 8;
    const uint32_t epi = aempty + (NA + 1) * 8;
    const uint32_t bar_bias = epi + 7 * 8;
    const uint32_t bar_l0 = bar_bias + 8;
    const uint32_t abig = sbase + SMEM_AB, asml = sbase + SMEM_AS;
    const bool lane0 = lane_id() == 0;
    const uint32_t wrel = mapa(sbase + SMEM_BAR + (2 + WG) * NW * 8, WG);
    const uint64_t descAb = mkdesc(abig, 16, 1024, 1);
    const uint64_t descAs = mkdesc(asml, 16, 512, 2);
    const uint64_t descW = mkdesc(sbase + (WG == 0 ? SMEM_W0 : SMEM_W1), 2048, 1024, 1);

    uint32_t wslot = 0, wphase = 0;
    bool wready = false;
    uint32_t rel_w = 0, rel_a = 0;
    uint32_t fslot = 0, fphase = 0;
    uint32_t nsm = 0;
    uint32_t nepi = 0;
    int stepno = 0;
    (void)stepno;

    float acc[2][N / 2];

    auto step = [&](uint64_t da, uint32_t mh_off, uint32_t a_rel, uint32_t peek_bar, uint32_t peek_par) -> bool {
        if (!wready) mbar_wait(bar_wfull + wslot * 8, wphase);
        const uint64_t db = descW + (uint64_t)(wslot * (WSTAGE >> 4));
        wgmma_fence();
        MMA<N>::run(acc[0], da, db);
        MMA<N>::run(acc[1], da + mh_off, db);
        wgmma_commit();
        if (w == 0 && lane0) TRACE(1 + WG * 4, stepno);
        stepno++;
        uint32_t nslot = wslot + 1, nphase = wphase;
        if (nslot == NW) { nslot = 0; nphase ^= 1; }
        wready = mbar_test(bar_wfull + nslot * 8, nphase);
        bool ok = true;
        if (peek_bar) ok = mbar_test(peek_bar, peek_par);
        wgmma_wait<1>();
        mbar_arrive_cluster_if(rel_w, lane0 && rel_w != 0);
        mbar_arrive_if(rel_a, lane0 && rel_a != 0);
        rel_w = wrel + wslot * 8;
        rel_a = a_rel;
        wslot = nslot;
        wphase = nphase;
        return ok;
    };

#pragma unroll 1
    for (int rd = 0; rd < NROUND; rd++) {
#pragma unroll
        for (int q = 0; q < N / 2; q++) { acc[0][q] = 0.f; acc[1][q] = 0.f; }
        uint32_t oslot = 0;
#pragma unroll 1
        for (int layer = 0; layer < NLAYER; layer++) {
            uint32_t s = 0, nb_slot, nb_bar, nb_par;
            auto next_block = [&](int blk) {
                const int ph = blk >= 7, b = blk - 7 * ph;
                const bool fresh = (layer == 0) || ph;
                if (b == 0) {
                    s = fresh ? fslot : oslot;
                    if (layer == 0 && ph) oslot = fslot;
                }
                nb_slot = b == 3 ? NA : s;
                if (fresh) {
                    nb_bar = afull + nb_slot * 8;
                    if (b == 3) {
                        nb_par = nsm & 1;
                        nsm++;
                    } else {
                        nb_par = fphase;
                        if (++fslot == NA) { fslot = 0; fphase ^= 1; }
                    }
                } else {
                    nb_bar = epi + b * 8;
                    nb_par = (nepi & 1) ^ 1;
                }
                if (b != 3 && ++s == NA) s = 0;
            };
            next_block(0);
            bool aready = false;
#pragma unroll 1
            for (int blk = 0; blk < 14; blk++) {
                if (!aready) mbar_wait(nb_bar, nb_par);
                if (WG == 1 && blk == 7 + LAG_BLOCK) asm volatile("bar.sync 3, 256;" ::: "memory");
                const bool small = nb_slot == NA;
                const bool release = (layer != 0) || (blk < 7);
                const uint64_t da = small ? descAs : descAb + (uint64_t)(nb_slot * (A_BIG >> 4));
                const uint32_t mh_off = small ? (A_SMALL >> 5) : (A_BIG >> 5);
                const uint32_t a_rel = release ? aempty + nb_slot * 8 : ((WG == 1 && small) ? bar_l0 : 0);
                if (!small) {
                    step(da + 4, mh_off, 0, 0, 0);
                    step(da + 6, mh_off, 0, 0, 0);
                }
                step(da, mh_off, 0, 0, 0);
                nb_bar = 0;
                if (blk < 13) next_block(blk + 1);
                aready = step(da + 2, mh_off, a_rel, nb_bar, nb_par);
            }
            if (WG == 0) asm volatile("bar.arrive 3, 256;" ::: "memory");
            uint32_t xphase = fphase;
            if (layer > 0) {
                oslot = fslot;
                fslot += 6;
                if (fslot >= NA) { fslot -= NA; fphase ^= 1; }
            } else {
                if (rd == 0) mbar_wait(bar_bias, 0);
                if (WG == 0) mbar_wait(bar_l0, rd & 1);
            }
            s = oslot + WG * 3;
            if (s >= NA) { s -= NA; xphase ^= 1; }
            if (layer > 0) {
                if (WG == 1) mbar_wait(afull + NA * 8, nsm & 1);
                else mbar_wait(afull + s * 8, xphase);
                nsm++;
            }
            const int lane = lane_id();
            const int erow = w * 16 + (lane & 15);
            const uint32_t eb = abig + erow * 128 + (((lane >> 4) ^ (erow & 7)) << 4);
            const uint32_t es = asml + erow * 64 + (((lane >> 4) ^ ((erow >> 1) & 3)) << 4);
            const uint32_t bl = sbase + SMEM_BIAS + (lane & 3) * 8 + WG * 12 * 32 + layer * (HALF_N * 2);
            constexpr int NCH = N / 16;
            uint32_t x[2][2][4], bv[2][2];
            uint32_t cur = WG == 1 ? es : eb + s * A_BIG, nxt = 0;
            ldsm_x4(x[0][0], cur);
            ldsm_x4(x[0][1], cur + (WG == 1 ? A_SMALL / 2 : A_BIG / 2));
            lds64(bv[0], bl + (WG == 1 ? 12 * 32 : 0));
            wgmma_wait<0>();
            mbar_arrive_cluster_if(rel_w, lane0);
            mbar_arrive_if(rel_a, lane0 && rel_a != 0);
            rel_w = 0;
            rel_a = 0;
            if (w == 0 && lane0) TRACE(2, ((rd * NLAYER + layer) * 2 + WG) * 2);
#pragma unroll
            for (int c = 0; c < NCH; c++) {
                const int cb = WG == 1 ? c - 2 : c;
                const bool small = cb < 0;
                if (c + 1 < NCH) {
                    const int nb = cb + 1;
                    if (nb < 0) {
                        nxt = cur ^ 32;
                    } else if ((nb & 3) == 0) {
                        if (nb > 0) {
                            if (++s == NA) { s = 0; xphase ^= 1; }
                        }
                        if (layer > 0) mbar_wait(afull + s * 8, xphase);
                        nxt = eb + s * A_BIG;
                    } else {
                        nxt = cur ^ ((((nb & 3) - 1) ^ (nb & 3)) << 5);
                    }
                    ldsm_x4(x[(c + 1) & 1][0], nxt);
                    ldsm_x4(x[(c + 1) & 1][1], nxt + (nb < 0 ? A_SMALL / 2 : A_BIG / 2));
                    lds64(bv[(c + 1) & 1], bl + (nb < 0 ? 13 : nb) * 32);
                }
                const int ai = small ? 96 + c * 8 : cb * 8;
                const uint32_t b0 = bv[c & 1][0], b1 = bv[c & 1][1];
#pragma unroll
                for (int mh = 0; mh < 2; mh++) {
                    epi_pair(x[c & 1][mh][0], acc[mh][ai + 0], acc[mh][ai + 1], b0);
                    epi_pair(x[c & 1][mh][1], acc[mh][ai + 2], acc[mh][ai + 3], b0);
                    epi_pair(x[c & 1][mh][2], acc[mh][ai + 4], acc[mh][ai + 5], b1);
                    epi_pair(x[c & 1][mh][3], acc[mh][ai + 6], acc[mh][ai + 7], b1);
                    stsm_x4(cur + mh * (small ? A_SMALL / 2 : A_BIG / 2), x[c & 1][mh]);
                }
                cur = nxt;
                if (cb == -1 || (cb >= 0 && (cb & 3) == 3)) {
                    asm volatile("fence.proxy.async.shared::cta;" ::: "memory");
                    __syncwarp();
                    mbar_arrive_if(epi + (cb < 0 ? 3 : WG * 4 + (cb >> 2)) * 8, lane0);
                }
            }
            nepi++;
            if (w == 0 && lane0) TRACE(2, ((rd * NLAYER + layer) * 2 + WG) * 2 + 1);
            if (layer == NLAYER - 1) {
                uint32_t q = oslot + WG * 3 + (lane >> 1);
                if (q >= NA) q -= NA;
                mbar_arrive_if(aempty + (lane >= 6 ? NA : q) * 8, lane < 6 + 2 * WG);
            }
        }
    }
}

__global__ void __cluster_dims__(2, 1, 1) __launch_bounds__(NTHREADS, 1)
dcn_kernel(const __grid_constant__ Maps maps, const __nv_bfloat16* __restrict__ x0,
           const __nv_bfloat16* __restrict__ bs) {
    extern __shared__ __align__(1024) uint8_t smem[];
    const uint32_t sbase = smem_u32(smem);
    const int tid = threadIdx.x;
    const int warp = __shfl_sync(0xffffffffu, tid >> 5, 0);
    const uint32_t rank = blockIdx.x & 1;
    const int cl = blockIdx.x >> 1;
    const int half = cl & 1;
    const int rb0 = (cl >> 1) * 2 + rank;

    const uint32_t bar_wfull = sbase + SMEM_BAR;
    const uint32_t bar_wempty = bar_wfull + 2 * NW * 8;
    const uint32_t afull = bar_wempty + 2 * NW * 8;
    const uint32_t aempty = afull + (NA + 1) * 8;
    const uint32_t epi = aempty + (NA + 1) * 8;
    const uint32_t bar_bias = epi + 7 * 8;
    const uint32_t bar_l0 = bar_bias + 8;
    const uint32_t stored = bar_l0 + 8;

    if (tid == 0) {
        TRACE(3, 0);
        GT(0);
        if (sbase & 1023) __trap();
        for (int i = 0; i < 2 * NW; i++) {
            mbar_init(bar_wfull + i * 8, 1);
            mbar_init(bar_wempty + i * 8, 8);
        }
        for (int i = 0; i < NA + 1; i++) {
            mbar_init(afull + i * 8, 1);
            mbar_init(aempty + i * 8, 8);
        }
        for (int i = 0; i < 7; i++) {
            mbar_init(epi + i * 8, 4);
            mbar_init(stored + i * 8, 1);
        }
        mbar_init(bar_bias, 32);
        mbar_init(bar_l0, 4);
        asm volatile("fence.mbarrier_init.release.cluster;" ::: "memory");
    }
    __syncthreads();
    cluster_sync_all();
    if (tid == 0) TRACE(3, 1);

    if (warp >= 8) {
        asm volatile("setmaxnreg.dec.sync.aligned.u32 24;");
        if ((warp & 1) == 0) {
            const uint32_t par = (warp >> 1) & 1;
            const uint32_t full = bar_wfull + rank * NW * 8, empty = bar_wempty + rank * NW * 8;
            const uint32_t peer_full = mapa(full, rank ^ 1);
            const uint32_t wbase = sbase + (rank ? SMEM_W1 : SMEM_W0);
            const uint32_t stage = rank ? W1_STAGE : W0_STAGE;
            uint32_t slot = par, phase = 0;
            int cnt = par;
            (void)cnt;
#pragma unroll 1
            for (int lp = 0; lp < NROUND * NLAYER * 2; lp++) {
                const int layer = (lp >> 1) % NLAYER;
                const int kh = half ^ (lp & 1) ^ (layer == 0);
                const int kb = layer * DIM + big_col(kh, 0), ks = layer * DIM + small_col(kh) - 16 * 12;
#pragma unroll 1
                for (int s = par; s < 26; s += 2) {
                    const int k = s < 12 ? kb + 16 * (s ^ 2) : (s < 14 ? ks + 16 * s : kb + 16 * ((s - 2) ^ 2));
                    mbar_wait(empty + slot * 8, phase ^ 1);
                    if (elect_one()) {
                        TRACE(0, cnt);
                        mbar_expect_tx(full + slot * 8, stage);
                        mbar_expect_tx_cluster(peer_full + slot * 8, stage);
                        const uint32_t dst = wbase + slot * stage;
                        tma3d_mc(dst, &maps.wb, 0, k, half * 7 + rank * 3, full + slot * 8, (uint16_t)3);
                        if (rank) tma3d_mc(dst + 3 * 2048, &maps.wsm, 0, k, half, full + slot * 8, (uint16_t)3);
                    }
                    __syncwarp();
                    cnt += 2;
                    slot += 2;
                    if (slot >= NW) { slot -= NW; phase ^= 1; }
                }
            }
        } else if (warp == 9) {
            const uint32_t abig = sbase + SMEM_AB, asml = sbase + SMEM_AS;
            uint32_t slot = 0, phase = 0;
            uint32_t nsm = 0;
            auto load_blk = [&](const CUtensorMap* mb, int kh, int b, int row) {
                if (b == 3) {
                    mbar_wait(aempty + NA * 8, (nsm & 1) ^ 1);
                    if (elect_one()) {
                        mbar_expect_tx(afull + NA * 8, A_SMALL);
                        tma2d_ld(asml, mb + 1, small_col(kh), row, afull + NA * 8);
                    }
                    nsm++;
                } else {
                    mbar_wait(aempty + slot * 8, phase ^ 1);
                    if (elect_one()) {
                        mbar_expect_tx(afull + slot * 8, A_BIG);
                        tma2d_ld(abig + slot * A_BIG, mb, big_col(kh, b - (b > 3)), row, afull + slot * 8);
                    }
                    if (++slot == NA) { slot = 0; phase ^= 1; }
                }
                __syncwarp();
            };
#pragma unroll 1
            for (int b = 0; b < 7; b++) {
                if (b >= 2 && b != 5) mbar_wait(afull + (b - 2 - (b > 5)) * 8, 0);
                load_blk(&maps.x0b, half ^ 1, b, rb0 * 128);
            }
#pragma unroll 1
            for (int lr = 0; lr < NROUND * NLAYER; lr++) {
                const int rd = lr / NLAYER, layer = lr - rd * NLAYER;
                const int rb = rb0 + rd * (NRB / NROUND);
                const int row = rb * 128;
#pragma unroll 1
                for (int b = 0; b < 7; b++) load_blk(&maps.x0b, half, b, row);
                if (lr + 1 < NROUND * NLAYER) {
                    const bool last = (layer == NLAYER - 1);
                    const CUtensorMap* mi = last ? &maps.x0b : ((ONEBUF || layer == 1) ? &maps.scrb : &maps.outb);
                    const int ri = last ? row + (NRB / NROUND) * 128 : ((ONEBUF || layer == 1) ? rb0 * 128 : row);
                    unsigned int* pfl = &g_flag[(((layer & 1) * NRB + rb) * 2 + (half ^ 1)) * FLAG_STRIDE];
#pragma unroll 1
                    for (int b = 0; b < 7; b++) {
                        if (b > 0) mbar_wait(stored + (b == 3 ? 3 : (b == 4 ? 2 : b - 1)) * 8, lr & 1);
                        if (!last) {
                            wait_flag(pfl, b + 1);
                            asm volatile("fence.proxy.async.global;" ::: "memory");
                            __syncwarp();
                            if (b == 6 && lane_id() == 0) *pfl = 0;
                        }
                        load_blk(mi, half ^ 1, b, ri);
                        if (rd + 1 < NROUND && !last && lane_id() == 0) {
                            const int piece = layer * 7 + b;
                            const int r0 = piece * 5 > 59 ? 59 : piece * 5;
                            const __nv_bfloat16* p = x0 + (size_t)(row + (NRB / NROUND) * 128 + half * 64 + r0) * DIM;
                            if (piece < 13)
                                asm volatile("cp.async.bulk.prefetch.L2.global [%0], %1;" ::"l"(p), "r"(5 * DIM * 2) : "memory");
                        }
                        __syncwarp();
                        if (lane_id() == 0) TRACE(7, lr * 7 + b);
                    }
                    mbar_wait(stored + 6 * 8, lr & 1);
                }
            }
        } else {
#pragma unroll 1
            for (int i = lane_id(); i < HALF_N; i += 32) {
                const int col = i < 384 ? big_col(half, 0) + i : small_col(half) + (i - 384);
                const int pos = (i >> 4) * 16 + ((i >> 1) & 3) * 4 + ((i >> 3) & 1) * 2 + (i & 1);
                float c = 0.f;
#pragma unroll
                for (int l = 0; l < NLAYER; l++) {
                    c += __bfloat162float(bs[l * DIM + col]);
                    reinterpret_cast<__nv_bfloat16*>(smem + SMEM_BIAS)[l * HALF_N + pos] = __float2bfloat16(c);
                }
            }
            mbar_arrive(bar_bias);
            const uint32_t abig = sbase + SMEM_AB, asml = sbase + SMEM_AS;
            uint32_t s = 6;
#pragma unroll 1
            for (int lr = 0; lr < NROUND * NLAYER; lr++) {
                const int rd = lr / NLAYER, layer = lr - rd * NLAYER;
                const int rb = rb0 + rd * (NRB / NROUND);
                const bool last = (layer == NLAYER - 1);
                const bool scr = ONEBUF ? !last : layer == 1;
                const CUtensorMap* mo = scr ? &maps.scrb : &maps.outb;
                const int ro = scr ? rb0 * 128 : rb * 128;
                unsigned int* myfl = &g_flag[(((layer & 1) * NRB + rb) * 2 + half) * FLAG_STRIDE];
#pragma unroll 1
                for (int b = 0; b < 7; b++) {
                    mbar_wait(epi + b * 8, lr & 1);
                    if (lane_id() == 0) {
                        TRACE(6, 100 + lr * 7 + b);
                        if (b == 3) tma2d_st(mo + 1, small_col(half), ro, asml);
                        else tma2d_st(mo, big_col(half, b - (b > 3)), ro, abig + s * A_BIG);
                        asm volatile("cp.async.bulk.commit_group;" ::: "memory");
                        if (!last) {
                            asm volatile("cp.async.bulk.wait_group 0;" ::: "memory");
                            TRACE(6, 200 + lr * 7 + b);
                            mbar_arrive(stored + b * 8);
                            asm volatile("fence.proxy.async.global;" ::: "memory");
                            asm volatile("st.release.gpu.global.u32 [%0], %1;" ::"l"(myfl), "r"(b + 1) : "memory");
                            if (b == 6) TRACE(4, lr);
                            TRACE(6, lr * 7 + b);
                        } else if (lr + 1 < NROUND * NLAYER) {
                            asm volatile("cp.async.bulk.wait_group.read 0;" ::: "memory");
                            mbar_arrive(stored + b * 8);
                            asm volatile("nanosleep.u32 %0;" ::"r"(STORE_PACE_NS));
                        }
                    }
                    __syncwarp();
                    if (b != 3 && ++s == NA) s = 0;
                }
                s += 6;
                if (s >= NA) s -= NA;
            }
            if (lane_id() == 0) {
                GT(1);
                asm volatile("cp.async.bulk.wait_group 0;" ::: "memory");
                GT(2);
            }
        }
        __syncwarp();
        cluster_sync_all();
    } else if (warp >= 4) {
        asm volatile("setmaxnreg.inc.sync.aligned.u32 256;");
        consumer<1>(sbase, warp & 3);
        __syncwarp();
        cluster_sync_all();
    } else {
        asm volatile("setmaxnreg.inc.sync.aligned.u32 224;");
        consumer<0>(sbase, warp & 3);
        __syncwarp();
        cluster_sync_all();
    }
}

typedef CUresult (*EncodeFn)(CUtensorMap*, CUtensorMapDataType, cuuint32_t, void*, const cuuint64_t*,
                             const cuuint64_t*, const cuuint32_t*, const cuuint32_t*, CUtensorMapInterleave,
                             CUtensorMapSwizzle, CUtensorMapL2promotion, CUtensorMapFloatOOBfill);

void make_x_maps(EncodeFn enc, CUtensorMap* big, CUtensorMap* small, void* ptr, int rows) {
    cuuint64_t gdim[2] = {(cuuint64_t)DIM, (cuuint64_t)rows};
    cuuint64_t gstr[1] = {(cuuint64_t)DIM * 2};
    cuuint32_t es[2] = {1, 1};
    cuuint32_t boxb[2] = {64, 128};
    enc(big, CU_TENSOR_MAP_DATA_TYPE_BFLOAT16, 2, ptr, gdim, gstr, boxb, es, CU_TENSOR_MAP_INTERLEAVE_NONE,
        CU_TENSOR_MAP_SWIZZLE_128B, CU_TENSOR_MAP_L2_PROMOTION_L2_128B, CU_TENSOR_MAP_FLOAT_OOB_FILL_NONE);
    cuuint32_t boxs[2] = {32, 128};
    enc(small, CU_TENSOR_MAP_DATA_TYPE_BFLOAT16, 2, ptr, gdim, gstr, boxs, es, CU_TENSOR_MAP_INTERLEAVE_NONE,
        CU_TENSOR_MAP_SWIZZLE_64B, CU_TENSOR_MAP_L2_PROMOTION_L2_64B, CU_TENSOR_MAP_FLOAT_OOB_FILL_NONE);
}

}

extern "C" void kernel_launch(void* const* d_in, const int* in_sizes, int n_in, void* d_out, int out_size) {
    const __nv_bfloat16* x0 = (const __nv_bfloat16*)d_in[0];
    const __nv_bfloat16* ws = (const __nv_bfloat16*)d_in[1];
    const __nv_bfloat16* bs = (const __nv_bfloat16*)d_in[2];

    static EncodeFn enc = nullptr;
    static void* scr = nullptr;
    if (!enc) {
        void* fn = nullptr;
        cudaDriverEntryPointQueryResult qr;
        cudaGetDriverEntryPoint("cuTensorMapEncodeTiled", &fn, cudaEnableDefault, &qr);
        enc = (EncodeFn)fn;
        cudaGetSymbolAddress(&scr, g_scr);
        cudaFuncSetAttribute(dcn_kernel, cudaFuncAttributeMaxDynamicSharedMemorySize, SMEM_TOTAL);
    }
    Maps maps;
    make_x_maps(enc, &maps.x0b, &maps.x0s, (void*)x0, BATCH);
    make_x_maps(enc, &maps.outb, &maps.outs, d_out, BATCH);
    make_x_maps(enc, &maps.scrb, &maps.scrs, scr, BATCH / NROUND);
    {
        cuuint64_t gdim[3] = {64, (cuuint64_t)NLAYER * DIM, 13};
        cuuint64_t gstr[2] = {(cuuint64_t)DIM * 2, 128};
        cuuint32_t box[3] = {64, 16, 3};
        cuuint32_t es[3] = {1, 1, 1};
        enc(&maps.wb, CU_TENSOR_MAP_DATA_TYPE_BFLOAT16, 3, (void*)ws, gdim, gstr, box, es, CU_TENSOR_MAP_INTERLEAVE_NONE,
            CU_TENSOR_MAP_SWIZZLE_128B, CU_TENSOR_MAP_L2_PROMOTION_L2_128B, CU_TENSOR_MAP_FLOAT_OOB_FILL_NONE);
        cuuint64_t gdim2[3] = {32, (cuuint64_t)NLAYER * DIM, 2};
        cuuint64_t gstr2[2] = {(cuuint64_t)DIM * 2, 64};
        cuuint32_t box2[3] = {64, 16, 1};
        enc(&maps.wsm, CU_TENSOR_MAP_DATA_TYPE_BFLOAT16, 3, (void*)(ws + 384), gdim2, gstr2, box2, es,
            CU_TENSOR_MAP_INTERLEAVE_NONE, CU_TENSOR_MAP_SWIZZLE_128B, CU_TENSOR_MAP_L2_PROMOTION_L2_64B,
            CU_TENSOR_MAP_FLOAT_OOB_FILL_NONE);
    }
    dcn_kernel<<<NRB, NTHREADS, SMEM_TOTAL>>>(maps, x0, bs);
}
```

```cpp
#include <cuda_runtime.h>
#include <cuda.h>
#include <cuda_bf16.h>
#include <stdint.h>

namespace {

constexpr int BATCH = 16384;
constexpr int DIM = 832;
constexpr int NLAYER = 3;
constexpr int HALF_N = 416;
constexpr int NRB = BATCH / 128;
constexpr int NROUND = 2;
constexpr int NPASS = NROUND * NLAYER;
constexpr int A_BIG = 16384;
constexpr int A_SMALL = 8192;
constexpr int NW0 = 9, NW1 = 8;
constexpr int NWM = 9;
constexpr int W0_STAGE = 3 * 2048;
constexpr int W1_STAGE = 4 * 2048;
constexpr int EARLY_W = 4;

constexpr int SMEM_AB = 0;
constexpr int SMEM_AS = SMEM_AB + 6 * A_BIG;
constexpr int SMEM_W0 = SMEM_AS + A_SMALL;
constexpr int SMEM_W1 = SMEM_W0 + NW0 * W0_STAGE;
constexpr int SMEM_BIAS = SMEM_W1 + NW1 * W1_STAGE;
constexpr int SMEM_BAR = SMEM_BIAS + NLAYER * HALF_N * 2;
constexpr int BAR_WFULL = 0;
constexpr int BAR_WEMPTY = 2 * NWM * 8;
constexpr int BAR_AFULL = 4 * NWM * 8;
constexpr int BAR_AEMPTY = BAR_AFULL + 56;
constexpr int BAR_EPI = BAR_AEMPTY + 56;
constexpr int BAR_STORED = BAR_EPI + 56;
constexpr int BAR_BIAS = BAR_STORED + 56;
constexpr int BAR_L0 = BAR_BIAS + 8;
constexpr int BAR_LAG = BAR_L0 + 8;
constexpr int SMEM_TOTAL = SMEM_BAR + BAR_LAG + 8;

constexpr int NTHREADS = 384;
constexpr int STORE_PACE_NS = 200;
constexpr int PUB_MASK = 0x6a;
constexpr int WPF_MASK = 0x13;

constexpr int FLAG_STRIDE = 64;
__device__ unsigned int g_flag[2 * NRB * 2 * FLAG_STRIDE];

__device__ __forceinline__ uint32_t smem_u32(const void* p) { return (uint32_t)__cvta_generic_to_shared(p); }
__device__ __forceinline__ void mbar_init(uint32_t bar, int cnt) {
    asm volatile("mbarrier.init.shared::cta.b64 [%0], %1;" ::"r"(bar), "r"(cnt));
}
__device__ __forceinline__ void mbar_expect_tx(uint32_t bar, uint32_t bytes) {
    asm volatile("mbarrier.arrive.expect_tx.shared::cta.b64 _, [%0], %1;" ::"r"(bar), "r"(bytes) : "memory");
}
__device__ __forceinline__ void mbar_expect_tx_cluster(uint32_t bar_cluster, uint32_t bytes) {
    asm volatile("mbarrier.arrive.expect_tx.shared::cluster.b64 _, [%0], %1;" ::"r"(bar_cluster), "r"(bytes) : "memory");
}
__device__ __forceinline__ void mbar_arrive(uint32_t bar) {
    asm volatile("mbarrier.arrive.shared::cta.b64 _, [%0];" ::"r"(bar) : "memory");
}
__device__ __forceinline__ void mbar_arrive_if(uint32_t bar, bool pred) {
    asm volatile("{\n.reg .pred p;\nsetp.ne.u32 p, %1, 0;\n@p mbarrier.arrive.shared::cta.b64 _, [%0];\n}\n" ::"r"(bar),
                 "r"((uint32_t)pred) : "memory");
}
__device__ __forceinline__ void mbar_arrive_cluster_if(uint32_t bar_cluster, bool pred) {
    asm volatile("{\n.reg .pred p;\nsetp.ne.u32 p, %1, 0;\n@p mbarrier.arrive.shared::cluster.b64 _, [%0];\n}\n" ::"r"(
                     bar_cluster), "r"((uint32_t)pred) : "memory");
}
__device__ __forceinline__ bool mbar_test(uint32_t bar, uint32_t parity) {
    uint32_t ok;
    asm volatile(
        "{\n.reg .pred p;\nmbarrier.test_wait.parity.shared::cta.b64 p, [%1], %2;\nselp.b32 %0, 1, 0, p;\n}\n"
        : "=r"(ok) : "r"(bar), "r"(parity) : "memory");
    return ok;
}
__device__ __forceinline__ void mbar_wait(uint32_t bar, uint32_t parity) {
    asm volatile(
        "{\n.reg .pred P1;\n.reg .u32 cnt;\n"
        "mbarrier.try_wait.parity.shared::cta.b64 P1, [%0], %1;\n"
        "@P1 bra DONE;\n"
        "mov.u32 cnt, 0;\n"
        "LAB_WAIT:\n"
        "mbarrier.try_wait.parity.shared::cta.b64 P1, [%0], %1;\n"
        "@P1 bra DONE;\n"
        "add.u32 cnt, cnt, 1;\n"
        "setp.lt.u32 P1, cnt, 4194304;\n"
        "@P1 bra LAB_WAIT;\n"
        "trap;\n"
        "DONE:\n}\n" ::"r"(bar), "r"(parity)
        : "memory");
}
__device__ __forceinline__ void mbar_wait_fast(uint32_t bar, uint32_t parity) {
    asm volatile(
        "{\n.reg .pred P1;\n"
        "LAB_WAIT:\n"
        "mbarrier.try_wait.parity.shared::cta.b64 P1, [%0], %1;\n"
        "@!P1 bra LAB_WAIT;\n}\n" ::"r"(bar), "r"(parity)
        : "memory");
}
__device__ __forceinline__ bool elect_one() {
    uint32_t p;
    asm volatile("{\n.reg .pred P;\nelect.sync _|P, 0xffffffff;\nselp.b32 %0, 1, 0, P;\n}\n" : "=r"(p));
    return p;
}
__device__ __forceinline__ void wait_flag(const unsigned int* flag, unsigned int target) {
    asm volatile(
        "{\n.reg .pred P1;\n.reg .u32 cnt, v;\n"
        "mov.u32 cnt, 0;\n"
        "LAB_WAIT:\n"
        "ld.acquire.gpu.global.u32 v, [%0];\n"
        "setp.ge.u32 P1, v, %1;\n"
        "@P1 bra DONE;\n"
        "nanosleep.u32 200;\n"
        "add.u32 cnt, cnt, 1;\n"
        "setp.lt.u32 P1, cnt, 4194304;\n"
        "@P1 bra LAB_WAIT;\n"
        "trap;\n"
        "DONE:\n}\n" ::"l"(flag), "r"(target)
        : "memory");
}
__device__ __forceinline__ void wait_flag_clear(const unsigned int* flag) {
    asm volatile(
        "{\n.reg .pred P1;\n.reg .u32 cnt, v;\n"
        "mov.u32 cnt, 0;\n"
        "LAB_WAIT:\n"
        "ld.acquire.gpu.global.u32 v, [%0];\n"
        "setp.eq.u32 P1, v, 0;\n"
        "@P1 bra DONE;\n"
        "nanosleep.u32 500;\n"
        "add.u32 cnt, cnt, 1;\n"
        "setp.lt.u32 P1, cnt, 4194304;\n"
        "@P1 bra LAB_WAIT;\n"
        "trap;\n"
        "DONE:\n}\n" ::"l"(flag)
        : "memory");
}
__device__ __forceinline__ int lane_id() {
    int l;
    asm volatile("mov.u32 %0, %%laneid;" : "=r"(l));
    return l;
}
__device__ __forceinline__ void lds64(uint32_t (&v)[2], uint32_t addr) {
    asm volatile("ld.shared.v2.u32 {%0,%1}, [%2];" : "=r"(v[0]), "=r"(v[1]) : "r"(addr));
}
__device__ __forceinline__ uint32_t mapa(uint32_t addr, uint32_t rank) {
    uint32_t r;
    asm volatile("mapa.shared::cluster.u32 %0, %1, %2;" : "=r"(r) : "r"(addr), "r"(rank));
    return r;
}
constexpr uint64_t L2_EVICT_NORMAL = 0x1000000000000000ull;
constexpr uint64_t L2_EVICT_FIRST = 0x12F0000000000000ull;
__device__ __forceinline__ void tma2d_ld(uint32_t dst, const CUtensorMap* tm, int c0, int c1, uint32_t bar, uint64_t pol) {
    asm volatile(
        "cp.async.bulk.tensor.2d.shared::cluster.global.mbarrier::complete_tx::bytes.L2::cache_hint "
        "[%0], [%1, {%3, %4}], [%2], %5;" ::"r"(dst),
        "l"(tm), "r"(bar), "r"(c0), "r"(c1), "l"(pol)
        : "memory");
}
__device__ __forceinline__ void tma2d_pf(const CUtensorMap* tm, int c0, int c1) {
    asm volatile("cp.async.bulk.prefetch.tensor.2d.L2.global [%0, {%1, %2}];" ::"l"(tm), "r"(c0), "r"(c1) : "memory");
}
__device__ __forceinline__ void tma2d_st(const CUtensorMap* tm, int c0, int c1, uint32_t src, uint64_t pol) {
    asm volatile("cp.async.bulk.tensor.2d.global.shared::cta.bulk_group.L2::cache_hint [%0, {%2, %3}], [%1], %4;" ::"l"(tm),
                 "r"(src), "r"(c0), "r"(c1), "l"(pol)
                 : "memory");
}
__device__ __forceinline__ void tma3d_mc(uint32_t dst, const CUtensorMap* tm, int c0, int c1, int c2, uint32_t bar,
                                         uint16_t mask) {
    asm volatile(
        "cp.async.bulk.tensor.3d.shared::cluster.global.mbarrier::complete_tx::bytes.multicast::cluster "
        "[%0], [%1, {%3, %4, %5}], [%2], %6;" ::"r"(dst), "l"(tm), "r"(bar), "r"(c0), "r"(c1), "r"(c2), "h"(mask)
        : "memory");
}
__device__ __forceinline__ void cluster_sync_all() {
    asm volatile("barrier.cluster.arrive.relaxed.aligned;\nbarrier.cluster.wait.aligned;" ::: "memory");
}

__device__ __forceinline__ void wgmma_n192(float (&d)[96], uint64_t da, uint64_t db, uint32_t accumulate) {
    asm volatile(
        "{\n.reg .pred p;\nsetp.ne.u32 p, %98, 0;\n"
        "wgmma.mma_async.sync.aligned.m64n192k16.f32.bf16.bf16 "
        "{%0, %1, %2, %3, %4, %5, %6, %7, %8, %9, %10, %11, %12, %13, %14, %15, "
        "%16, %17, %18, %19, %20, %21, %22, %23, %24, %25, %26, %27, %28, %29, %30, %31, "
        "%32, %33, %34, %35, %36, %37, %38, %39, %40, %41, %42, %43, %44, %45, %46, %47, "
        "%48, %49, %50, %51, %52, %53, %54, %55, %56, %57, %58, %59, %60, %61, %62, %63, "
        "%64, %65, %66, %67, %68, %69, %70, %71, %72, %73, %74, %75, %76, %77, %78, %79, "
        "%80, %81, %82, %83, %84, %85, %86, %87, %88, %89, %90, %91, %92, %93, %94, %95}, %96, %97, p, 1, 1, 0, 1;\n}\n"
        : "+f"(d[0]), "+f"(d[1]), "+f"(d[2]), "+f"(d[3]), "+f"(d[4]), "+f"(d[5]), "+f"(d[6]), "+f"(d[7]),
          "+f"(d[8]), "+f"(d[9]), "+f"(d[10]), "+f"(d[11]), "+f"(d[12]), "+f"(d[13]), "+f"(d[14]), "+f"(d[15]),
          "+f"(d[16]), "+f"(d[17]), "+f"(d[18]), "+f"(d[19]), "+f"(d[20]), "+f"(d[21]), "+f"(d[22]), "+f"(d[23]),
          "+f"(d[24]), "+f"(d[25]), "+f"(d[26]), "+f"(d[27]), "+f"(d[28]), "+f"(d[29]), "+f"(d[30]), "+f"(d[31]),
          "+f"(d[32]), "+f"(d[33]), "+f"(d[34]), "+f"(d[35]), "+f"(d[36]), "+f"(d[37]), "+f"(d[38]), "+f"(d[39]),
          "+f"(d[40]), "+f"(d[41]), "+f"(d[42]), "+f"(d[43]), "+f"(d[44]), "+f"(d[45]), "+f"(d[46]), "+f"(d[47]),
          "+f"(d[48]), "+f"(d[49]), "+f"(d[50]), "+f"(d[51]), "+f"(d[52]), "+f"(d[53]), "+f"(d[54]), "+f"(d[55]),
          "+f"(d[56]), "+f"(d[57]), "+f"(d[58]), "+f"(d[59]), "+f"(d[60]), "+f"(d[61]), "+f"(d[62]), "+f"(d[63]),
          "+f"(d[64]), "+f"(d[65]), "+f"(d[66]), "+f"(d[67]), "+f"(d[68]), "+f"(d[69]), "+f"(d[70]), "+f"(d[71]),
          "+f"(d[72]), "+f"(d[73]), "+f"(d[74]), "+f"(d[75]), "+f"(d[76]), "+f"(d[77]), "+f"(d[78]), "+f"(d[79]),
          "+f"(d[80]), "+f"(d[81]), "+f"(d[82]), "+f"(d[83]), "+f"(d[84]), "+f"(d[85]), "+f"(d[86]), "+f"(d[87]),
          "+f"(d[88]), "+f"(d[89]), "+f"(d[90]), "+f"(d[91]), "+f"(d[92]), "+f"(d[93]), "+f"(d[94]), "+f"(d[95])
        : "l"(da), "l"(db), "r"(accumulate));
}
__device__ __forceinline__ void wgmma_n224(float (&d)[112], uint64_t da, uint64_t db, uint32_t accumulate) {
    asm volatile(
        "{\n.reg .pred p;\nsetp.ne.u32 p, %114, 0;\n"
        "wgmma.mma_async.sync.aligned.m64n224k16.f32.bf16.bf16 "
        "{%0, %1, %2, %3, %4, %5, %6, %7, %8, %9, %10, %11, %12, %13, %14, %15, "
        "%16, %17, %18, %19, %20, %21, %22, %23, %24, %25, %26, %27, %28, %29, %30, %31, "
        "%32, %33, %34, %35, %36, %37, %38, %39, %40, %41, %42, %43, %44, %45, %46, %47, "
        "%48, %49, %50, %51, %52, %53, %54, %55, %56, %57, %58, %59, %60, %61, %62, %63, "
        "%64, %65, %66, %67, %68, %69, %70, %71, %72, %73, %74, %75, %76, %77, %78, %79, "
        "%80, %81, %82, %83, %84, %85, %86, %87, %88, %89, %90, %91, %92, %93, %94, %95, "
        "%96, %97, %98, %99, %100, %101, %102, %103, %104, %105, %106, %107, %108, %109, %110, %111}, %112, %113, p, 1, 1, 0, 1;\n}\n"
        : "+f"(d[0]), "+f"(d[1]), "+f"(d[2]), "+f"(d[3]), "+f"(d[4]), "+f"(d[5]), "+f"(d[6]), "+f"(d[7]),
          "+f"(d[8]), "+f"(d[9]), "+f"(d[10]), "+f"(d[11]), "+f"(d[12]), "+f"(d[13]), "+f"(d[14]), "+f"(d[15]),
          "+f"(d[16]), "+f"(d[17]), "+f"(d[18]), "+f"(d[19]), "+f"(d[20]), "+f"(d[21]), "+f"(d[22]), "+f"(d[23]),
          "+f"(d[24]), "+f"(d[25]), "+f"(d[26]), "+f"(d[27]), "+f"(d[28]), "+f"(d[29]), "+f"(d[30]), "+f"(d[31]),
          "+f"(d[32]), "+f"(d[33]), "+f"(d[34]), "+f"(d[35]), "+f"(d[36]), "+f"(d[37]), "+f"(d[38]), "+f"(d[39]),
          "+f"(d[40]), "+f"(d[41]), "+f"(d[42]), "+f"(d[43]), "+f"(d[44]), "+f"(d[45]), "+f"(d[46]), "+f"(d[47]),
          "+f"(d[48]), "+f"(d[49]), "+f"(d[50]), "+f"(d[51]), "+f"(d[52]), "+f"(d[53]), "+f"(d[54]), "+f"(d[55]),
          "+f"(d[56]), "+f"(d[57]), "+f"(d[58]), "+f"(d[59]), "+f"(d[60]), "+f"(d[61]), "+f"(d[62]), "+f"(d[63]),
          "+f"(d[64]), "+f"(d[65]), "+f"(d[66]), "+f"(d[67]), "+f"(d[68]), "+f"(d[69]), "+f"(d[70]), "+f"(d[71]),
          "+f"(d[72]), "+f"(d[73]), "+f"(d[74]), "+f"(d[75]), "+f"(d[76]), "+f"(d[77]), "+f"(d[78]), "+f"(d[79]),
          "+f"(d[80]), "+f"(d[81]), "+f"(d[82]), "+f"(d[83]), "+f"(d[84]), "+f"(d[85]), "+f"(d[86]), "+f"(d[87]),
          "+f"(d[88]), "+f"(d[89]), "+f"(d[90]), "+f"(d[91]), "+f"(d[92]), "+f"(d[93]), "+f"(d[94]), "+f"(d[95]),
          "+f"(d[96]), "+f"(d[97]), "+f"(d[98]), "+f"(d[99]), "+f"(d[100]), "+f"(d[101]), "+f"(d[102]), "+f"(d[103]),
          "+f"(d[104]), "+f"(d[105]), "+f"(d[106]), "+f"(d[107]), "+f"(d[108]), "+f"(d[109]), "+f"(d[110]), "+f"(d[111])
        : "l"(da), "l"(db), "r"(accumulate));
}
__device__ __forceinline__ void wgmma_fence() { asm volatile("wgmma.fence.sync.aligned;" ::: "memory"); }
__device__ __forceinline__ void wgmma_commit() { asm volatile("wgmma.commit_group.sync.aligned;" ::: "memory"); }
template <int N>
__device__ __forceinline__ void wgmma_wait() { asm volatile("wgmma.wait_group.sync.aligned %0;" ::"n"(N) : "memory"); }

__device__ __forceinline__ void ldsm_x4(uint32_t (&v)[4], uint32_t addr) {
    asm volatile("ldmatrix.sync.aligned.m8n8.x4.shared.b16 {%0,%1,%2,%3}, [%4];"
                 : "=r"(v[0]), "=r"(v[1]), "=r"(v[2]), "=r"(v[3]) : "r"(addr) : "memory");
}
__device__ __forceinline__ void stsm_x4(uint32_t addr, const uint32_t (&v)[4]) {
    asm volatile("stmatrix.sync.aligned.m8n8.x4.shared.b16 [%0], {%1,%2,%3,%4};" ::"r"(addr), "r"(v[0]), "r"(v[1]),
                 "r"(v[2]), "r"(v[3]) : "memory");
}

__device__ __forceinline__ void epi_pair(uint32_t& x, float a0, float a1, uint32_t bias) {
    asm volatile(
        "{\n.reg .b32 t;\n"
        "cvt.rn.bf16x2.f32 t, %2, %1;\n"
        "add.rn.bf16x2 t, t, %3;\n"
        "fma.rn.bf16x2 %0, %0, t, %0;\n}\n"
        : "+r"(x) : "f"(a0), "f"(a1), "r"(bias));
}

__device__ __forceinline__ int big_col(int half, int i) { return (half ? 448 : 0) + 64 * i; }
__device__ __forceinline__ int small_col(int half) { return half ? 416 : 384; }

struct C2 { static constexpr int value = 2; };
struct C4 { static constexpr int value = 4; };

struct Maps {
    CUtensorMap x0b, x0s, outb, outs, wb, wsm;
};

template <int N> struct MMA;
template <> struct MMA<192> {
    static __device__ __forceinline__ void run(float (&d)[96], uint64_t a, uint64_t b, uint32_t c) { wgmma_n192(d, a, b, c); }
};
template <> struct MMA<224> {
    static __device__ __forceinline__ void run(float (&d)[112], uint64_t a, uint64_t b, uint32_t c) { wgmma_n224(d, a, b, c); }
};

template <int WG>
__device__ __forceinline__ void consumer(const uint32_t sbase, const int w) {
    constexpr int N = WG == 0 ? 192 : 224;
    constexpr int WSTAGE = WG == 0 ? W0_STAGE : W1_STAGE;
    const uint32_t bars = sbase + SMEM_BAR;
    constexpr int NW = WG == 0 ? NW0 : NW1;
    const uint32_t bar_wfull = bars + BAR_WFULL + WG * NWM * 8;
    const bool lane0 = lane_id() == 0;
    const uint32_t wrel = mapa(bars + BAR_WEMPTY + WG * NWM * 8, WG);
    const uint32_t a_lo = ((sbase & 0x3FFFF) >> 4) | (1u << 16);
    const uint32_t w_lo = (((sbase + (WG == 0 ? SMEM_W0 : SMEM_W1)) & 0x3FFFF) >> 4) | ((2048u >> 4) << 16);

    uint32_t wslot = 0, wpar = 0, wprev = 0;
    bool wready = false;
    uint32_t rel_a = 0;
    bool rel_w = false;

    float acc[2][N / 2];
#pragma unroll
    for (int q = 0; q < N / 2; q++) { acc[0][q] = 0.f; acc[1][q] = 0.f; }
    uint32_t accum = 0;

    auto block = [&](auto nsteps_c, uint32_t alo, uint32_t next_bar, uint32_t next_par, uint32_t rel_bar,
                     uint32_t mid_bar, uint32_t mid_par) -> bool {
        constexpr int NSTEPS = decltype(nsteps_c)::value;
        constexpr uint64_t hi_a = NSTEPS == 2 ? (uint64_t)(0x80000000u | (512u >> 4)) : (uint64_t)(0x40000000u | (1024u >> 4));
        bool ok = false;
#pragma unroll
        for (int st = 0; st < NSTEPS; st++) {
            const uint32_t slot = wslot;
            if (!wready) mbar_wait_fast(bar_wfull + slot * 8, wpar);
            const uint64_t da = (hi_a << 32) | (uint64_t)(alo + 2 * st);
            const uint64_t db = ((uint64_t)(0x40000000u | (1024u >> 4)) << 32) | (uint64_t)(w_lo + slot * (WSTAGE >> 4));
            wgmma_fence();
            const uint32_t sc = (st == 0 && NSTEPS == 4) ? accum : 1u;
            MMA<N>::run(acc[0], da, db, sc);
            MMA<N>::run(acc[1], da + ((NSTEPS == 2 ? A_SMALL : A_BIG) >> 5), db, sc);
            wgmma_commit();
            accum = 1;
            if (++wslot == NW) { wslot = 0; wpar ^= 1; }
            wready = mbar_test(bar_wfull + wslot * 8, wpar);
            if (st == NSTEPS - 1) ok = mbar_test(next_bar, next_par);
            if (WG == 1 && NSTEPS == 2 && st == 0) ok = mbar_test(mid_bar, mid_par);
            wgmma_wait<1>();
            if (st == 0) {
                mbar_arrive_cluster_if(wrel + wprev * 8, lane0 && rel_w);
                mbar_arrive_if(rel_a, lane0 && rel_a != 0);
                rel_w = true;
                if (WG == 1 && NSTEPS == 2) {
                    if (!ok) mbar_wait_fast(mid_bar, mid_par);
                }
            } else {
                mbar_arrive_cluster_if(wrel + wprev * 8, lane0);
            }
            wprev = slot;
        }
        rel_a = rel_bar;
        return ok;
    };
    auto phase = [&](uint32_t guard, uint32_t gpar, uint32_t nguard, uint32_t ngpar, uint32_t rel, uint32_t rel2,
                     bool lag_sync, bool aready, uint32_t pre, uint32_t prepar) -> bool {
        uint32_t alo = a_lo + (SMEM_AB >> 4);
#pragma unroll 1
        for (int b = 0; b < 7; b++) {
            if (pre) {
                mbar_wait_fast(pre + b * 8, prepar);
                aready = false;
            }
            if (!aready) mbar_wait_fast(guard + b * 8, gpar);
            const bool lastb = b == 6;
            aready = block(C4{}, alo, lastb ? nguard : guard + b * 8 + 8, lastb ? ngpar : gpar,
                           b == 2 ? rel2 : (rel ? rel + b * 8 : 0), 0, 0);
            alo += A_BIG >> 4;
            if (b == 2) {
                b = 3;
                if (pre) {
                    mbar_wait_fast(pre + 3 * 8, prepar);
                    aready = false;
                }
                if (!aready) mbar_wait_fast(guard + 3 * 8, gpar);
                aready = block(C2{}, a_lo + (SMEM_AS >> 4), guard + 4 * 8, gpar, rel ? rel + 3 * 8 : 0,
                               lag_sync ? bars + BAR_LAG : guard + 3 * 8, lag_sync ? prepar ^ 1 : gpar);
            }
        }
        return aready;
    };

#pragma unroll 1
    for (int lr = 0; lr < NPASS; lr++) {
        const int layer = lr % NLAYER;
        if (layer == 0) accum = 0;
        bool aready = false;
#pragma unroll 1
        for (int ph = 0; ph < 2; ph++) {
            const bool own = (layer != 0) && (ph == 0);
            const bool keep = (layer == 0) && (ph == 1);
            const uint32_t guard = bars + (own ? BAR_EPI : BAR_AFULL);
            const uint32_t gpar = own ? ((lr & 1) ^ 1) : (keep ? 1 : 0);
            const uint32_t rel = keep ? 0 : bars + BAR_AEMPTY;
            const uint32_t rel2 = keep ? (WG == 1 ? bars + BAR_L0 : 0) : bars + BAR_AEMPTY + 2 * 8;
            const uint32_t pre = (layer == 0 && ph == 0 && lr > 0) ? bars + BAR_EPI : 0;
            aready = phase(guard, gpar, bars + BAR_AFULL, layer == 0 ? 1 : 0, rel, rel2, ph == 1, aready, pre,
                           (lr & 1) ^ 1);
        }
        if (WG == 0) mbar_arrive_if(bars + BAR_LAG, lane0);

        if (layer == 0) {
            if (lr == 0) mbar_wait_fast(bars + BAR_BIAS, 0);
            if (WG == 0) mbar_wait_fast(bars + BAR_L0, lr & 1);
            else mbar_wait_fast(bars + BAR_EPI, lr & 1);
        } else {
            mbar_wait_fast(bars + BAR_AFULL + WG * 3 * 8, 1);
        }
        const int lane = lane_id();
        const int erow = w * 16 + (lane & 15);
        const uint32_t eb = sbase + SMEM_AB + WG * 3 * A_BIG + erow * 128 + (((lane >> 4) ^ (erow & 7)) << 4);
        const uint32_t es = sbase + SMEM_AS + erow * 64 + (((lane >> 4) ^ ((erow >> 1) & 3)) << 4);
        const uint32_t bl = sbase + SMEM_BIAS + (lane & 3) * 8 + WG * 12 * 32 + layer * (HALF_N * 2);
        constexpr int NCH = N / 16;
        auto caddr = [&](int cb) -> uint32_t {
            return cb < 0 ? es ^ ((cb + 2) << 5) : (eb ^ ((cb & 3) << 5)) + (cb >> 2) * A_BIG;
        };
        auto iaddr = [&](int it) -> uint32_t {
            const int cb = (it >> 1) - 2 * WG;
            return caddr(cb) + (it & 1) * (cb < 0 ? A_SMALL / 2 : A_BIG / 2);
        };
        uint32_t x[3][4], bv[2][2];
        ldsm_x4(x[0], iaddr(0));
        ldsm_x4(x[1], iaddr(1));
        lds64(bv[0], bl + (WG == 1 ? 12 * 32 : 0));
        wgmma_wait<0>();
        mbar_arrive_cluster_if(wrel + wprev * 8, lane0);
        mbar_arrive_if(rel_a, lane0 && rel_a != 0);
        rel_w = false;
        rel_a = 0;
#pragma unroll
        for (int it = 0; it < 2 * NCH; it++) {
            const int c = it >> 1, mh = it & 1;
            const int cb = c - 2 * WG;
            if (it + 2 < 2 * NCH) {
                const int nb = cb + 1;
                if (mh == 0) {
                    if (nb >= 0 && (nb & 3) == 0) {
                        if (layer > 0) mbar_wait_fast(bars + BAR_AFULL + (WG * 4 + (nb >> 2)) * 8, 1);
                    }
                    lds64(bv[(c + 1) & 1], bl + (nb < 0 ? 13 : nb) * 32);
                }
                ldsm_x4(x[(it + 2) % 3], iaddr(it + 2));
            }
            const int ai = cb < 0 ? 96 + c * 8 : cb * 8;
            const uint32_t b0 = bv[c & 1][0], b1 = bv[c & 1][1];
            epi_pair(x[it % 3][0], acc[mh][ai + 0], acc[mh][ai + 1], b0);
            epi_pair(x[it % 3][1], acc[mh][ai + 2], acc[mh][ai + 3], b0);
            epi_pair(x[it % 3][2], acc[mh][ai + 4], acc[mh][ai + 5], b1);
            epi_pair(x[it % 3][3], acc[mh][ai + 6], acc[mh][ai + 7], b1);
            stsm_x4(iaddr(it), x[it % 3]);
            if (mh == 1 && (cb == -1 || (cb >= 0 && (cb & 3) == 3))) {
                asm volatile("fence.proxy.async.shared::cta;" ::: "memory");
                __syncwarp();
                const int b = cb < 0 ? 3 : WG * 4 + (cb >> 2);
                mbar_arrive_if(bars + BAR_EPI + b * 8, lane0);
            }
        }
    }
}

__global__ void __cluster_dims__(2, 1, 1) __launch_bounds__(NTHREADS, 1)
dcn_kernel(const __grid_constant__ Maps maps, const __nv_bfloat16* __restrict__ x0,
           const __nv_bfloat16* __restrict__ ws, const __nv_bfloat16* __restrict__ bs) {
    extern __shared__ __align__(1024) uint8_t smem[];
    const uint32_t sbase = smem_u32(smem);
    const int tid = threadIdx.x;
    const int warp = __shfl_sync(0xffffffffu, tid >> 5, 0);
    const uint32_t rank = blockIdx.x & 1;
    const int cl = blockIdx.x >> 1;
    const int half = (cl >> 3) & 1;
    const int q = ((cl >> 4) << 3) | (cl & 7);
    const int rb0 = q * 2 + rank;
    const uint32_t bars = sbase + SMEM_BAR;

    if (tid == 0) {
        if (sbase & 1023) __trap();
    }
    if (tid < 128) {
        const __nv_bfloat16* p = x0 + (size_t)(rb0 * 128 + tid) * DIM + big_col(half ^ 1, 0);
        asm volatile("prefetch.global.L2 [%0];" ::"l"(p));
    } else if (tid < 128 + 56) {
        const int idx = tid - 128 + (q & 3) * 56, r = idx / 7, ln = idx - r * 7;
        const __nv_bfloat16* p = ws + (size_t)(big_col(half ^ 1, 0) + r) * DIM + half * 384 + ln * 64;
        asm volatile("prefetch.global.L2 [%0];" ::"l"(p));
    }
    if (warp == 9) {
        if (elect_one()) {
#pragma unroll
            for (int i = 0; i < 7; i++) mbar_init(bars + BAR_AFULL + i * 8, 1);
#pragma unroll
            for (int i = 0; i < 2 * NWM; i++) {
                mbar_init(bars + BAR_WFULL + i * 8, 1);
                mbar_init(bars + BAR_WEMPTY + i * 8, 8);
            }
#pragma unroll
            for (int i = 0; i < 7; i++) {
                mbar_init(bars + BAR_AEMPTY + i * 8, 8);
                mbar_init(bars + BAR_EPI + i * 8, 4);
                mbar_init(bars + BAR_STORED + i * 8, 1);
            }
            mbar_init(bars + BAR_BIAS, 32);
            mbar_init(bars + BAR_L0, 4);
            mbar_init(bars + BAR_LAG, 4);
            asm volatile("fence.mbarrier_init.release.cluster;" ::: "memory");
        }
    }
    __syncwarp();
    asm volatile("barrier.cluster.arrive.relaxed.aligned;" ::: "memory");
    if (warp == 9) {
        if (elect_one()) {
            mbar_expect_tx(bars + BAR_AFULL, A_BIG);
            tma2d_ld(sbase + SMEM_AB, &maps.x0b, big_col(half ^ 1, 0), rb0 * 128, bars + BAR_AFULL, L2_EVICT_NORMAL);
        }
        __syncwarp();
    }
    if (tid == 32) {
        asm volatile("prefetch.tensormap [%0];" ::"l"(&maps.wb) : "memory");
        asm volatile("prefetch.tensormap [%0];" ::"l"(&maps.wsm) : "memory");
        asm volatile("prefetch.tensormap [%0];" ::"l"(&maps.x0s) : "memory");
    }
    __syncwarp();
    asm volatile("barrier.cluster.wait.aligned;" ::: "memory");
    if (warp == 8) {
        if (elect_one()) {
            const uint32_t full = bars + BAR_WFULL + rank * NWM * 8;
            const uint32_t peer_full = mapa(full, rank ^ 1);
            const uint32_t stage = rank ? W1_STAGE : W0_STAGE;
#pragma unroll
            for (int i = 0; i < EARLY_W; i++) {
                const uint32_t dst = sbase + (rank ? SMEM_W1 : SMEM_W0) + i * stage;
                const int k = big_col(half ^ 1, 0) + 16 * i;
                mbar_expect_tx(full + i * 8, stage);
                mbar_expect_tx_cluster(peer_full + i * 8, stage);
                tma3d_mc(dst, &maps.wb, 0, k, half * 7 + rank * 3, full + i * 8, (uint16_t)3);
                if (rank) tma3d_mc(dst + 3 * 2048, &maps.wsm, 0, k, half, full + i * 8, (uint16_t)3);
            }
        }
        __syncwarp();
    }

    if (warp >= 8) {
        asm volatile("setmaxnreg.dec.sync.aligned.u32 24;");
        if ((warp & 1) == 0) {
            const uint32_t par = (warp >> 1) & 1;
            const uint32_t full = bars + BAR_WFULL + rank * NWM * 8, empty = bars + BAR_WEMPTY + rank * NWM * 8;
            const uint32_t nw = rank ? NW1 : NW0;
            const uint32_t peer_full = mapa(full, rank ^ 1);
            const uint32_t wbase = sbase + (rank ? SMEM_W1 : SMEM_W0);
            const uint32_t stage = rank ? W1_STAGE : W0_STAGE;
            uint32_t slot = par + EARLY_W, epar = 1;
#pragma unroll 1
            for (int lp = 0; lp < NPASS * 2; lp++) {
                const int layer = (lp >> 1) % NLAYER;
                const int kh = half ^ (lp & 1) ^ (layer == 0);
                const int kb = layer * DIM + big_col(kh, 0), ks = layer * DIM + small_col(kh) - 16 * 12;
#pragma unroll 1
                for (int s = par + (lp == 0 ? EARLY_W : 0); s < 26; s += 2) {
                    const int k = s < 12 ? kb + 16 * s : (s < 14 ? ks + 16 * s : kb + 16 * (s - 2));
                    mbar_wait(empty + slot * 8, epar);
                    if (elect_one()) {
                        mbar_expect_tx(full + slot * 8, stage);
                        mbar_expect_tx_cluster(peer_full + slot * 8, stage);
                        const uint32_t dst = wbase + slot * stage;
                        tma3d_mc(dst, &maps.wb, 0, k, half * 7 + rank * 3, full + slot * 8, (uint16_t)3);
                        if (rank) tma3d_mc(dst + 3 * 2048, &maps.wsm, 0, k, half, full + slot * 8, (uint16_t)3);
                    }
                    __syncwarp();
                    slot += 2;
                    if (slot >= nw) { slot -= nw; epar ^= 1; }
                }
            }
        } else if (warp == 9) {
            auto load_blk = [&](const CUtensorMap* mb, int kh, int b, int row, uint32_t epar, bool last_use) {
                const uint64_t pol = last_use ? L2_EVICT_FIRST : L2_EVICT_NORMAL;
                mbar_wait(bars + BAR_AEMPTY + b * 8, epar);
                if (elect_one()) {
                    const uint32_t fb = bars + BAR_AFULL + b * 8;
                    if (b == 3) {
                        mbar_expect_tx(fb, A_SMALL);
                        tma2d_ld(sbase + SMEM_AS, mb + 1, small_col(kh), row, fb, pol);
                    } else {
                        const int i = b - (b > 3);
                        mbar_expect_tx(fb, A_BIG);
                        tma2d_ld(sbase + SMEM_AB + i * A_BIG, mb, big_col(kh, i), row, fb, pol);
                    }
                }
                __syncwarp();
            };
#pragma unroll 1
            for (int b = 1; b < 7; b++) {
                if (b >= 2) mbar_wait(bars + BAR_AFULL + (b - 2) * 8, 0);
                load_blk(&maps.x0b, half ^ 1, b, rb0 * 128, 1, false);
            }
#pragma unroll 1
            for (int lr = 0; lr < NPASS; lr++) {
                const int rd = lr / NLAYER, layer = lr - rd * NLAYER;
                const int rb = rb0 + rd * (NRB / NROUND);
                const int row = rb * 128;
                if (((WPF_MASK >> lr) & 1) && lane_id() == 0) {
                    const int nl = layer + 1 == NLAYER ? 0 : layer + 1;
                    const __nv_bfloat16* p = ws + (size_t)nl * DIM * DIM + (size_t)blockIdx.x * (DIM * DIM / NRB);
                    asm volatile("cp.async.bulk.prefetch.L2.global [%0], %1;" ::"l"(p), "r"(DIM * DIM / NRB * 2) : "memory");
                }
                __syncwarp();
#pragma unroll 1
                for (int b = 0; b < 7; b++) {
                    load_blk(&maps.x0b, half, b, row, rd & 1, layer == NLAYER - 1);
                    if (b < 3 && rd + 1 < NROUND && layer == NLAYER - 1) {
                        if (elect_one()) tma2d_pf(&maps.x0b, big_col(half ^ 1, b), row + (NRB / NROUND) * 128);
                        __syncwarp();
                    }
                }
                if (layer < NLAYER - 1) {
                    unsigned int* pfl = &g_flag[((layer * NRB + rb) * 2 + (half ^ 1)) * FLAG_STRIDE];
#pragma unroll 1
                    for (int b = 0; b < 7; b++) {
                        mbar_wait(bars + BAR_STORED + b * 8, layer);
                        wait_flag(pfl, b + 1);
                        asm volatile("fence.proxy.async.global;" ::: "memory");
                        __syncwarp();
                        load_blk(&maps.outb, half ^ 1, b, row, (rd & 1) ^ 1, true);
                    }
#pragma unroll 1
                    for (int b = 0; b < 7; b++) mbar_wait(bars + BAR_AFULL + b * 8, 0);
                    if (lane_id() == 0) asm volatile("st.relaxed.gpu.global.u32 [%0], 0;" ::"l"(pfl) : "memory");
                    __syncwarp();
                }
            }
        } else {
#pragma unroll 1
            for (int i = lane_id(); i < HALF_N; i += 32) {
                const int col = i < 384 ? big_col(half, 0) + i : small_col(half) + (i - 384);
                const int pos = (i >> 4) * 16 + ((i >> 1) & 3) * 4 + ((i >> 3) & 1) * 2 + (i & 1);
                float c = 0.f;
#pragma unroll
                for (int l = 0; l < NLAYER; l++) {
                    c += __bfloat162float(bs[l * DIM + col]);
                    reinterpret_cast<__nv_bfloat16*>(smem + SMEM_BIAS)[l * HALF_N + pos] = __float2bfloat16(c);
                }
            }
            mbar_arrive(bars + BAR_BIAS);
#pragma unroll 1
            for (int lr = 0; lr < NPASS; lr++) {
                const int rd = lr / NLAYER, layer = lr - rd * NLAYER;
                const int rb = rb0 + rd * (NRB / NROUND);
                const int row = rb * 128;
                const bool last = (layer == NLAYER - 1);
                unsigned int* myfl = &g_flag[(((layer & 1) * NRB + rb) * 2 + half) * FLAG_STRIDE];
                if (layer > 0) wait_flag_clear(&g_flag[(((layer - 1) * NRB + rb) * 2 + half) * FLAG_STRIDE]);
#pragma unroll 1
                for (int b = 0; b < 7; b++) {
                    mbar_wait(bars + BAR_EPI + b * 8, lr & 1);
                    if (lane_id() == 0) {
                        const uint64_t pol = last ? L2_EVICT_FIRST : L2_EVICT_NORMAL;
                        const int i = b - (b > 3);
                        if (b == 3) tma2d_st(&maps.outs, small_col(half), row, sbase + SMEM_AS, pol);
                        else tma2d_st(&maps.outb, big_col(half, i), row, sbase + SMEM_AB + i * A_BIG, pol);
                        asm volatile("cp.async.bulk.commit_group;" ::: "memory");
                        if (!last) {
                            asm volatile("cp.async.bulk.wait_group 0;" ::: "memory");
                            mbar_arrive(bars + BAR_STORED + b * 8);
                            if ((PUB_MASK >> b) & 1) {
                                asm volatile("fence.proxy.async.global;" ::: "memory");
                                asm volatile("st.release.gpu.global.u32 [%0], %1;" ::"l"(myfl), "r"(b + 1) : "memory");
                            } else {
                                asm volatile("nanosleep.u32 %0;" ::"r"(STORE_PACE_NS));
                            }
                        } else if (lr + 1 < NPASS) {
                            asm volatile("cp.async.bulk.wait_group.read 0;" ::: "memory");
                            const uint32_t fb = bars + BAR_AFULL + b * 8;
                            const int rn = row + (NRB / NROUND) * 128;
                            mbar_expect_tx(fb, b == 3 ? A_SMALL : A_BIG);
                            if (b == 3) tma2d_ld(sbase + SMEM_AS, &maps.x0s, small_col(half ^ 1), rn, fb, L2_EVICT_NORMAL);
                            else tma2d_ld(sbase + SMEM_AB + i * A_BIG, &maps.x0b, big_col(half ^ 1, i), rn, fb, L2_EVICT_NORMAL);
                            asm volatile("nanosleep.u32 %0;" ::"r"(STORE_PACE_NS));
                        }
                    }
                    __syncwarp();
                }
            }
            if (lane_id() == 0) {
                asm volatile("cp.async.bulk.wait_group 0;" ::: "memory");
            }
        }
        __syncwarp();
        cluster_sync_all();
    } else if (warp >= 4) {
        asm volatile("setmaxnreg.inc.sync.aligned.u32 256;");
        consumer<1>(sbase, warp & 3);
        __syncwarp();
        cluster_sync_all();
    } else {
        asm volatile("setmaxnreg.inc.sync.aligned.u32 224;");
        consumer<0>(sbase, warp & 3);
        __syncwarp();
        cluster_sync_all();
    }
}

typedef CUresult (*EncodeFn)(CUtensorMap*, CUtensorMapDataType, cuuint32_t, void*, const cuuint64_t*,
                             const cuuint64_t*, const cuuint32_t*, const cuuint32_t*, CUtensorMapInterleave,
                             CUtensorMapSwizzle, CUtensorMapL2promotion, CUtensorMapFloatOOBfill);

void make_x_maps(EncodeFn enc, CUtensorMap* big, CUtensorMap* small, void* ptr) {
    cuuint64_t gdim[2] = {(cuuint64_t)DIM, (cuuint64_t)BATCH};
    cuuint64_t gstr[1] = {(cuuint64_t)DIM * 2};
    cuuint32_t es[2] = {1, 1};
    cuuint32_t boxb[2] = {64, 128};
    enc(big, CU_TENSOR_MAP_DATA_TYPE_BFLOAT16, 2, ptr, gdim, gstr, boxb, es, CU_TENSOR_MAP_INTERLEAVE_NONE,
        CU_TENSOR_MAP_SWIZZLE_128B, CU_TENSOR_MAP_L2_PROMOTION_L2_128B, CU_TENSOR_MAP_FLOAT_OOB_FILL_NONE);
    cuuint32_t boxs[2] = {32, 128};
    enc(small, CU_TENSOR_MAP_DATA_TYPE_BFLOAT16, 2, ptr, gdim, gstr, boxs, es, CU_TENSOR_MAP_INTERLEAVE_NONE,
        CU_TENSOR_MAP_SWIZZLE_64B, CU_TENSOR_MAP_L2_PROMOTION_L2_64B, CU_TENSOR_MAP_FLOAT_OOB_FILL_NONE);
}

}

extern "C" void kernel_launch(void* const* d_in, const int* in_sizes, int n_in, void* d_out, int out_size) {
    const __nv_bfloat16* x0 = (const __nv_bfloat16*)d_in[0];
    const __nv_bfloat16* ws = (const __nv_bfloat16*)d_in[1];
    const __nv_bfloat16* bs = (const __nv_bfloat16*)d_in[2];

    static EncodeFn enc = nullptr;
    if (!enc) {
        void* fn = nullptr;
        cudaDriverEntryPointQueryResult qr;
        cudaGetDriverEntryPoint("cuTensorMapEncodeTiled", &fn, cudaEnableDefault, &qr);
        enc = (EncodeFn)fn;
        cudaFuncSetAttribute(dcn_kernel, cudaFuncAttributeMaxDynamicSharedMemorySize, SMEM_TOTAL);
    }
    Maps maps;
    make_x_maps(enc, &maps.x0b, &maps.x0s, (void*)x0);
    make_x_maps(enc, &maps.outb, &maps.outs, d_out);
    {
        cuuint64_t gdim[3] = {64, (cuuint64_t)NLAYER * DIM, 13};
        cuuint64_t gstr[2] = {(cuuint64_t)DIM * 2, 128};
        cuuint32_t box[3] = {64, 16, 3};
        cuuint32_t es[3] = {1, 1, 1};
        enc(&maps.wb, CU_TENSOR_MAP_DATA_TYPE_BFLOAT16, 3, (void*)ws, gdim, gstr, box, es, CU_TENSOR_MAP_INTERLEAVE_NONE,
            CU_TENSOR_MAP_SWIZZLE_128B, CU_TENSOR_MAP_L2_PROMOTION_L2_128B, CU_TENSOR_MAP_FLOAT_OOB_FILL_NONE);
        cuuint64_t gdim2[3] = {32, (cuuint64_t)NLAYER * DIM, 2};
        cuuint64_t gstr2[2] = {(cuuint64_t)DIM * 2, 64};
        cuuint32_t box2[3] = {64, 16, 1};
        enc(&maps.wsm, CU_TENSOR_MAP_DATA_TYPE_BFLOAT16, 3, (void*)(ws + 384), gdim2, gstr2, box2, es,
            CU_TENSOR_MAP_INTERLEAVE_NONE, CU_TENSOR_MAP_SWIZZLE_128B, CU_TENSOR_MAP_L2_PROMOTION_L2_64B,
            CU_TENSOR_MAP_FLOAT_OOB_FILL_NONE);
    }
    dcn_kernel<<<NRB, NTHREADS, SMEM_TOTAL>>>(maps, x0, ws, bs);
}
```
